```python
import torch

def _softmax(x, axis=-1):
    return torch.softmax(x, dim=axis)
def _gelu(x):
    return torch.nn.functional.gelu(x, approximate="tanh")
def _silu(x):
    return torch.nn.functional.silu(x)
def _sigmoid(x):
    return torch.sigmoid(x)
def _layernorm(x, axis=-1, eps=1e-5):
    m = x.mean(dim=axis, keepdim=True)
    v = x.var(dim=axis, keepdim=True, unbiased=False)
    return (x - m) / torch.sqrt(v + eps)
def _scatter_add(tgt, idx, src, axis=0):
    return tgt.clone().index_add_(axis, idx, src)
def _segment_sum(src, seg, n):
    out = torch.zeros((n,) + src.shape[1:], dtype=src.dtype)
    return out.index_add_(0, seg, src)
def _pad(x, pw):
    flat = tuple(v for pair in reversed(pw) for v in pair)
    return torch.nn.functional.pad(x, flat)

kernel_name = 'sequential_preLN__gqa_block_cached__glu_gated_geglu__decode'

def setup_inputs():

    _w = (lambda a: (lambda t: t.to(torch.bfloat16) if t.is_floating_point() else t)(torch.as_tensor(a)))
    def _A_setup():
        B, Sq, D = 4, 1, 512
        Hq, Hkv, Sk, Dh = 32, 8, 4096, 128
        assert Hq % Hkv == 0, (Hq, Hkv)
        return {
            "x": _w((lambda *s: torch.randn(*s, dtype=torch.bfloat16) * 0.05)(B, Sq, D)),
            "k_cache": _w((lambda *s: torch.randn(*s, dtype=torch.bfloat16) * 1.6)(B, Hkv, Sk, Dh)),
            "v_cache": _w((lambda *s: torch.randn(*s, dtype=torch.bfloat16) * 0.8)(B, Hkv, Sk, Dh)),
            "wq": _w((lambda *s: torch.randn(*s, dtype=torch.bfloat16) * 1.6)(D, Hq * Dh) * (D ** -0.5)),
            "wo": _w((lambda *s: torch.randn(*s, dtype=torch.bfloat16) * 0.8)(Hq * Dh, D) * ((Hq * Dh) ** -0.5)),
        }
    _A_in = _A_setup()

    def _B_setup():
        B, S, Dm, Df = 4, 1, 512, 1792
        return {
            "x": _w((lambda *s: torch.randn(*s, dtype=torch.bfloat16) * 0.05)(B, S, Dm)),
            "w_gate": _w((lambda *s: torch.randn(*s, dtype=torch.bfloat16) * 0.8)(Dm, Df) * (Dm ** -0.5)),
            "w_up": _w((lambda *s: torch.randn(*s, dtype=torch.bfloat16) * 0.8)(Dm, Df) * (Dm ** -0.5)),
            "w_down": _w((lambda *s: torch.randn(*s, dtype=torch.bfloat16) * 0.8)(Df, Dm) * (Df ** -0.5)),
        }
    _B_in = _B_setup()

    return {
        "A_x": _A_in["x"],
        "A_k_cache": _A_in["k_cache"],
        "A_v_cache": _A_in["v_cache"],
        "A_wq": _A_in["wq"],
        "A_wo": _A_in["wo"],
        "B_x": _B_in["x"],
        "B_w_gate": _B_in["w_gate"],
        "B_w_up": _B_in["w_up"],
        "B_w_down": _B_in["w_down"],
    }

def reference(A_x, A_k_cache, A_v_cache, A_wq, A_wo, B_x, B_w_gate, B_w_up, B_w_down):
    def _A_ref(x, k_cache, v_cache, wq, wo):
        B, Sq, D = x.shape
        Hq, Dh = 32, 128
        Hkv = k_cache.shape[1]
        rep = Hq // Hkv
        q = (lambda x, *d: x.permute(*d))((x @ wq).reshape(B, Sq, Hq, Dh), 0, 2, 1, 3)
        k = (lambda x, n, axis: torch.repeat_interleave(x, n, dim=axis))(k_cache, rep, axis=1)
        v = (lambda x, n, axis: torch.repeat_interleave(x, n, dim=axis))(v_cache, rep, axis=1)
        scores = torch.einsum("bhqd,bhkd->bhqk", q, k) * (Dh ** -0.5)
        p = _softmax(scores, axis=-1)
        o = torch.einsum("bhqk,bhkd->bhqd", p, v)
        return (lambda x, *d: x.permute(*d))(o, 0, 2, 1, 3).reshape(B, Sq, Hq * Dh) @ wo

    def _B_ref(x, w_gate, w_up, w_down):
        g = torch.einsum("bsd,df->bsf", x, w_gate)
        u = torch.einsum("bsd,df->bsf", x, w_up)
        h = _gelu(g) * u
        return torch.einsum("bsf,fd->bsd", h, w_down)

    x = A_x
    h = x + _A_ref(_layernorm(x, axis=-1), A_k_cache, A_v_cache, A_wq, A_wo)
    h2 = h + _B_ref(_layernorm(h, axis=-1), B_w_gate, B_w_up, B_w_down)
    return h2
```

```cpp
#include <cuda_runtime.h>
#include <cuda_bf16.h>
#include <stdint.h>

namespace {

constexpr int NCTA = 128;
constexpr int NTHREADS = 256;
constexpr int NWARPS = 8;
constexpr int D = 512;
constexpr int SK = 4096;
constexpr int DF = 1792;
constexpr int NFFN = 112;
constexpr int SPIN_LIMIT = 1 << 24;

__device__ __nv_bfloat16 g_q[4 * 4096];
__device__ float g_part_o[NCTA * 4 * 128];
__device__ float g_part_ml[NCTA * 4 * 2];
__device__ float g_attn[4 * 512];
__device__ float g_final[4 * 512];
__device__ unsigned int g_bar[4];

constexpr int SM_WO = 0;
constexpr int SM_WG = SM_WO + 256 * 64 * 2;
constexpr int SM_WU = SM_WG + 512 * 16 * 2;
constexpr int SM_WD = SM_WU + 512 * 16 * 2;
constexpr int SM_XN = SM_WD + 16 * 512 * 2;
constexpr int SM_RED = SM_XN + 512 * 4 * 4;
constexpr int SM_MISC = SM_RED + 16384;
constexpr int SM_TOTAL = SM_MISC + 4096;

__device__ __forceinline__ uint4 ldg_stream(const void* p) {
    uint4 r;
    asm volatile("ld.global.nc.L1::no_allocate.L2::128B.v4.u32 {%0,%1,%2,%3}, [%4];"
                 : "=r"(r.x), "=r"(r.y), "=r"(r.z), "=r"(r.w) : "l"(p));
    return r;
}
__device__ __forceinline__ void cp_async16(uint32_t saddr, const void* g) {
    asm volatile("cp.async.cg.shared.global [%0], [%1], 16;" :: "r"(saddr), "l"(g));
}
__device__ __forceinline__ void mma_bf16(float (&c)[4], uint32_t a0, uint32_t a1, uint32_t a2, uint32_t a3,
                                         uint32_t b0, uint32_t b1) {
    asm volatile("mma.sync.aligned.m16n8k16.row.col.f32.bf16.bf16.f32 {%0,%1,%2,%3}, {%4,%5,%6,%7}, {%8,%9}, {%0,%1,%2,%3};"
                 : "+f"(c[0]), "+f"(c[1]), "+f"(c[2]), "+f"(c[3])
                 : "r"(a0), "r"(a1), "r"(a2), "r"(a3), "r"(b0), "r"(b1));
}
__device__ __forceinline__ uint32_t pack_bf16(float lo, float hi) {
    __nv_bfloat162 v = __floats2bfloat162_rn(lo, hi);
    return *reinterpret_cast<uint32_t*>(&v);
}
__device__ __forceinline__ float bf_lo(uint32_t v) { return __uint_as_float(v << 16); }
__device__ __forceinline__ float bf_hi(uint32_t v) { return __uint_as_float(v & 0xffff0000u); }
__device__ __forceinline__ float round_bf(float v) { return __bfloat162float(__float2bfloat16_rn(v)); }

__device__ __forceinline__ void grid_barrier(unsigned int* ctr, unsigned int target) {
    __syncthreads();
    if (threadIdx.x == 0) {
        __threadfence();
        atomicAdd(ctr, 1u);
        unsigned int v;
        int it = 0;
        do {
            asm volatile("ld.acquire.gpu.global.u32 %0, [%1];" : "=r"(v) : "l"(ctr) : "memory");
            if (++it > SPIN_LIMIT) __trap();
        } while (v < target);
    }
    __syncthreads();
}

__device__ __forceinline__ float warp_sum(float v) {
#pragma unroll
    for (int o = 16; o > 0; o >>= 1) v += __shfl_xor_sync(0xffffffffu, v, o);
    return v;
}

__global__ void __launch_bounds__(NTHREADS, 1)
fused_block_kernel(const __nv_bfloat16* __restrict__ x,
                   const __nv_bfloat16* __restrict__ kc,
                   const __nv_bfloat16* __restrict__ vc,
                   const __nv_bfloat16* __restrict__ wq,
                   const __nv_bfloat16* __restrict__ wo,
                   const __nv_bfloat16* __restrict__ wg,
                   const __nv_bfloat16* __restrict__ wu,
                   const __nv_bfloat16* __restrict__ wd,
                   __nv_bfloat16* __restrict__ out) {
    extern __shared__ __align__(128) unsigned char smem[];
    const uint32_t sbase = (uint32_t)__cvta_generic_to_shared(smem);
    const int tid = threadIdx.x;
    const int warp = tid >> 5;
    const int lane = tid & 31;
    const int cta = blockIdx.x;
    const int g = lane >> 2;
    const int c = lane & 3;

    float* xn = reinterpret_cast<float*>(smem + SM_XN);
    float* red = reinterpret_cast<float*>(smem + SM_RED);
    float* misc = reinterpret_cast<float*>(smem + SM_MISC);

    uint4 wqr[8];
    {
        const int cg = tid & 3, rg = tid >> 2;
        const __nv_bfloat16* p = wq + (size_t)(rg * 8) * 4096 + cta * 32 + cg * 8;
#pragma unroll
        for (int i = 0; i < 8; i++) wqr[i] = ldg_stream(p + (size_t)i * 4096);
    }
    const int bh = cta >> 2;
    const int split = cta & 3;
    const int batch = bh >> 3;
    const int hkv = bh & 7;
    const __nv_bfloat16* kbase = kc + ((size_t)bh * SK + split * 1024 + warp * 128) * 128;
    const __nv_bfloat16* vbase = vc + ((size_t)bh * SK + split * 1024 + warp * 128) * 128;
    uint4 kr[8], vr[8];
#pragma unroll
    for (int j = 0; j < 4; j++) {
        kr[j] = ldg_stream(kbase + (size_t)g * 128 + 32 * j + 8 * c);
        kr[4 + j] = ldg_stream(kbase + (size_t)(g + 8) * 128 + 32 * j + 8 * c);
    }
#pragma unroll
    for (int hf = 0; hf < 2; hf++) {
        vr[hf * 4 + 0] = ldg_stream(vbase + (size_t)(2 * c) * 128 + hf * 64 + g * 8);
        vr[hf * 4 + 1] = ldg_stream(vbase + (size_t)(2 * c + 1) * 128 + hf * 64 + g * 8);
        vr[hf * 4 + 2] = ldg_stream(vbase + (size_t)(2 * c + 8) * 128 + hf * 64 + g * 8);
        vr[hf * 4 + 3] = ldg_stream(vbase + (size_t)(2 * c + 9) * 128 + hf * 64 + g * 8);
    }
    const int kcI = cta >> 3;
    const int ncI = cta & 7;
    {
#pragma unroll
        for (int i = 0; i < 8; i++) {
            int ch = tid + i * 256;
            int r = ch >> 3, pt = ch & 7;
            cp_async16(sbase + SM_WO + r * 128 + pt * 16, wo + (size_t)(kcI * 256 + r) * 512 + ncI * 64 + pt * 8);
        }
        if (cta < NFFN) {
#pragma unroll
            for (int i = 0; i < 4; i++) {
                int ch = tid + i * 256;
                int r = ch >> 1, pt = ch & 1;
                cp_async16(sbase + SM_WG + r * 32 + pt * 16, wg + (size_t)r * DF + cta * 16 + pt * 8);
                cp_async16(sbase + SM_WU + r * 32 + pt * 16, wu + (size_t)r * DF + cta * 16 + pt * 8);
                cp_async16(sbase + SM_WD + ch * 16, wd + (size_t)cta * 16 * 512 + ch * 8);
            }
        }
        asm volatile("cp.async.commit_group;");
    }
    if (cta == 0) {
        for (int i = tid; i < 2048; i += NTHREADS) { g_attn[i] = 0.f; g_final[i] = 0.f; }
    }
    if (warp < 4) {
        float v[16];
        const uint4* xp = reinterpret_cast<const uint4*>(x + warp * 512 + lane * 16);
        uint4 a = xp[0], b = xp[1];
        uint32_t w[8] = {a.x, a.y, a.z, a.w, b.x, b.y, b.z, b.w};
        float s = 0.f;
#pragma unroll
        for (int i = 0; i < 8; i++) { v[2 * i] = bf_lo(w[i]); v[2 * i + 1] = bf_hi(w[i]); s += v[2 * i] + v[2 * i + 1]; }
        float mean = warp_sum(s) * (1.f / 512.f);
        float q = 0.f;
#pragma unroll
        for (int i = 0; i < 16; i++) { float d = v[i] - mean; q += d * d; }
        float var = warp_sum(q) * (1.f / 512.f);
        float rstd = rsqrtf(var + 1e-5f);
#pragma unroll
        for (int i = 0; i < 16; i++) xn[(lane * 16 + i) * 4 + warp] = round_bf((v[i] - mean) * rstd);
    }
    __syncthreads();
    {
        const int cg = tid & 3, rg = tid >> 2;
        float acc[4][8];
#pragma unroll
        for (int b = 0; b < 4; b++)
#pragma unroll
            for (int j = 0; j < 8; j++) acc[b][j] = 0.f;
#pragma unroll
        for (int i = 0; i < 8; i++) {
            float4 xv = *reinterpret_cast<const float4*>(xn + (rg * 8 + i) * 4);
            uint32_t w[4] = {wqr[i].x, wqr[i].y, wqr[i].z, wqr[i].w};
#pragma unroll
            for (int j = 0; j < 4; j++) {
                float lo = bf_lo(w[j]), hi = bf_hi(w[j]);
                acc[0][2 * j] += xv.x * lo; acc[0][2 * j + 1] += xv.x * hi;
                acc[1][2 * j] += xv.y * lo; acc[1][2 * j + 1] += xv.y * hi;
                acc[2][2 * j] += xv.z * lo; acc[2][2 * j + 1] += xv.z * hi;
                acc[3][2 * j] += xv.w * lo; acc[3][2 * j + 1] += xv.w * hi;
            }
        }
#pragma unroll
        for (int b = 0; b < 4; b++)
#pragma unroll
            for (int j = 0; j < 8; j++) {
                float v = acc[b][j];
                v += __shfl_xor_sync(0xffffffffu, v, 4);
                v += __shfl_xor_sync(0xffffffffu, v, 8);
                v += __shfl_xor_sync(0xffffffffu, v, 16);
                acc[b][j] = v;
            }
        if (lane < 4) {
#pragma unroll
            for (int b = 0; b < 4; b++)
#pragma unroll
                for (int j = 0; j < 8; j++) red[(warp * 4 + b) * 32 + cg * 8 + j] = acc[b][j];
        }
        __syncthreads();
        if (tid < 128) {
            int b = tid >> 5, col = tid & 31;
            float s = 0.f;
#pragma unroll
            for (int w = 0; w < 8; w++) s += red[(w * 4 + b) * 32 + col];
            g_q[b * 4096 + cta * 32 + col] = __float2bfloat16_rn(s);
        }
    }
    grid_barrier(&g_bar[0], NCTA);

    uint32_t qf[16];
    {
        if (g < 4) {
            const __nv_bfloat16* qp = g_q + batch * 4096 + (hkv * 4 + g) * 128 + 8 * c;
#pragma unroll
            for (int j = 0; j < 4; j++) {
                uint4 t = __ldcg(reinterpret_cast<const uint4*>(qp + 32 * j));
                qf[4 * j] = t.x; qf[4 * j + 1] = t.y; qf[4 * j + 2] = t.z; qf[4 * j + 3] = t.w;
            }
        } else {
#pragma unroll
            for (int j = 0; j < 16; j++) qf[j] = 0u;
        }
    }
    const float sc = 0.08838834764831845f * 1.4426950408889634f;
    float oacc[16][4];
#pragma unroll
    for (int t = 0; t < 16; t++) { oacc[t][0] = oacc[t][1] = oacc[t][2] = oacc[t][3] = 0.f; }
    float mrun = -INFINITY, lrun = 0.f;

#pragma unroll 1
    for (int it = 0; it < 8; it++) {
        float s0[4] = {0.f, 0.f, 0.f, 0.f}, s1[4] = {0.f, 0.f, 0.f, 0.f};
#pragma unroll
        for (int j = 0; j < 4; j++) {
            mma_bf16(s0, qf[4 * j], 0u, qf[4 * j + 1], 0u, kr[j].x, kr[j].y);
            mma_bf16(s0, qf[4 * j + 2], 0u, qf[4 * j + 3], 0u, kr[j].z, kr[j].w);
            mma_bf16(s1, qf[4 * j], 0u, qf[4 * j + 1], 0u, kr[4 + j].x, kr[4 + j].y);
            mma_bf16(s1, qf[4 * j + 2], 0u, qf[4 * j + 3], 0u, kr[4 + j].z, kr[4 + j].w);
        }
        if (it < 7) {
            const __nv_bfloat16* kp = kbase + (size_t)(it + 1) * 16 * 128;
#pragma unroll
            for (int j = 0; j < 4; j++) {
                kr[j] = ldg_stream(kp + (size_t)g * 128 + 32 * j + 8 * c);
                kr[4 + j] = ldg_stream(kp + (size_t)(g + 8) * 128 + 32 * j + 8 * c);
            }
        }
        float a0 = s0[0] * sc, a1 = s0[1] * sc, a2 = s1[0] * sc, a3 = s1[1] * sc;
        float mx = fmaxf(fmaxf(a0, a1), fmaxf(a2, a3));
        mx = fmaxf(mx, __shfl_xor_sync(0xffffffffu, mx, 1));
        mx = fmaxf(mx, __shfl_xor_sync(0xffffffffu, mx, 2));
        float mnew = fmaxf(mrun, mx);
        float corr = exp2f(mrun - mnew);
        mrun = mnew;
        float p0 = exp2f(a0 - mnew), p1 = exp2f(a1 - mnew), p2 = exp2f(a2 - mnew), p3 = exp2f(a3 - mnew);
        uint32_t pa0 = pack_bf16(p0, p1), pa2 = pack_bf16(p2, p3);
        lrun = lrun * corr + (bf_lo(pa0) + bf_hi(pa0) + bf_lo(pa2) + bf_hi(pa2));
#pragma unroll
        for (int t = 0; t < 16; t++) { oacc[t][0] *= corr; oacc[t][1] *= corr; }
#pragma unroll
        for (int hf = 0; hf < 2; hf++) {
            uint32_t va[4] = {vr[hf * 4 + 0].x, vr[hf * 4 + 0].y, vr[hf * 4 + 0].z, vr[hf * 4 + 0].w};
            uint32_t vb[4] = {vr[hf * 4 + 1].x, vr[hf * 4 + 1].y, vr[hf * 4 + 1].z, vr[hf * 4 + 1].w};
            uint32_t vcc[4] = {vr[hf * 4 + 2].x, vr[hf * 4 + 2].y, vr[hf * 4 + 2].z, vr[hf * 4 + 2].w};
            uint32_t vd[4] = {vr[hf * 4 + 3].x, vr[hf * 4 + 3].y, vr[hf * 4 + 3].z, vr[hf * 4 + 3].w};
#pragma unroll
            for (int i = 0; i < 4; i++) {
                uint32_t b0 = __byte_perm(va[i], vb[i], 0x5410);
                uint32_t b1 = __byte_perm(vcc[i], vd[i], 0x5410);
                mma_bf16(oacc[hf * 8 + 2 * i], pa0, 0u, pa2, 0u, b0, b1);
                uint32_t b2 = __byte_perm(va[i], vb[i], 0x7632);
                uint32_t b3 = __byte_perm(vcc[i], vd[i], 0x7632);
                mma_bf16(oacc[hf * 8 + 2 * i + 1], pa0, 0u, pa2, 0u, b2, b3);
            }
        }
        if (it < 7) {
            const __nv_bfloat16* vp = vbase + (size_t)(it + 1) * 16 * 128;
#pragma unroll
            for (int hf = 0; hf < 2; hf++) {
                vr[hf * 4 + 0] = ldg_stream(vp + (size_t)(2 * c) * 128 + hf * 64 + g * 8);
                vr[hf * 4 + 1] = ldg_stream(vp + (size_t)(2 * c + 1) * 128 + hf * 64 + g * 8);
                vr[hf * 4 + 2] = ldg_stream(vp + (size_t)(2 * c + 8) * 128 + hf * 64 + g * 8);
                vr[hf * 4 + 3] = ldg_stream(vp + (size_t)(2 * c + 9) * 128 + hf * 64 + g * 8);
            }
        }
    }
    lrun += __shfl_xor_sync(0xffffffffu, lrun, 1);
    lrun += __shfl_xor_sync(0xffffffffu, lrun, 2);
    if (g < 4) {
#pragma unroll
        for (int t = 0; t < 16; t++) {
            int hf = t >> 3, i = t & 7;
            red[(warp * 4 + g) * 128 + hf * 64 + (2 * c) * 8 + i] = oacc[t][0];
            red[(warp * 4 + g) * 128 + hf * 64 + (2 * c + 1) * 8 + i] = oacc[t][1];
        }
        if (c == 0) { misc[(warp * 4 + g) * 2] = mrun; misc[(warp * 4 + g) * 2 + 1] = lrun; }
    }
    __syncthreads();
    {
#pragma unroll
        for (int r = 0; r < 2; r++) {
            int idx = tid + r * 256;
            int h = idx >> 7, d = idx & 127;
            float M = -INFINITY;
#pragma unroll
            for (int w = 0; w < 8; w++) M = fmaxf(M, misc[(w * 4 + h) * 2]);
            float o = 0.f, L = 0.f;
#pragma unroll
            for (int w = 0; w < 8; w++) {
                float f = exp2f(misc[(w * 4 + h) * 2] - M);
                o += f * red[(w * 4 + h) * 128 + d];
                L += f * misc[(w * 4 + h) * 2 + 1];
            }
            g_part_o[(cta * 4 + h) * 128 + d] = o;
            if (d == 0) { g_part_ml[(cta * 4 + h) * 2] = M; g_part_ml[(cta * 4 + h) * 2 + 1] = L; }
        }
    }
    grid_barrier(&g_bar[1], NCTA);

    {
        const int hq = 2 * kcI + (tid >> 7);
        const int hk = hq >> 2, hg = hq & 3;
        const int d = tid & 127;
        float ov[4];
#pragma unroll
        for (int b = 0; b < 4; b++) {
            const int base = (b * 8 + hk) * 4;
            float m[4], l[4], o[4];
#pragma unroll
            for (int s = 0; s < 4; s++) {
                m[s] = __ldcg(&g_part_ml[((base + s) * 4 + hg) * 2]);
                l[s] = __ldcg(&g_part_ml[((base + s) * 4 + hg) * 2 + 1]);
                o[s] = __ldcg(&g_part_o[((base + s) * 4 + hg) * 128 + d]);
            }
            float M = fmaxf(fmaxf(m[0], m[1]), fmaxf(m[2], m[3]));
            float L = 0.f, acc = 0.f;
#pragma unroll
            for (int s = 0; s < 4; s++) { float f = exp2f(m[s] - M); L += f * l[s]; acc += f * o[s]; }
            ov[b] = round_bf(acc / L);
        }
        *reinterpret_cast<float4*>(xn + tid * 4) = make_float4(ov[0], ov[1], ov[2], ov[3]);
    }
    asm volatile("cp.async.wait_group 0;" ::: "memory");
    __syncthreads();
    {
        float a[4][2];
#pragma unroll
        for (int b = 0; b < 4; b++) { a[b][0] = 0.f; a[b][1] = 0.f; }
        const uint32_t* wos = reinterpret_cast<const uint32_t*>(smem + SM_WO);
#pragma unroll 8
        for (int k = warp * 32; k < warp * 32 + 32; k++) {
            uint32_t w = wos[k * 32 + lane];
            float4 ovv = *reinterpret_cast<const float4*>(xn + k * 4);
            float lo = bf_lo(w), hi = bf_hi(w);
            a[0][0] += ovv.x * lo; a[0][1] += ovv.x * hi;
            a[1][0] += ovv.y * lo; a[1][1] += ovv.y * hi;
            a[2][0] += ovv.z * lo; a[2][1] += ovv.z * hi;
            a[3][0] += ovv.w * lo; a[3][1] += ovv.w * hi;
        }
#pragma unroll
        for (int b = 0; b < 4; b++) {
            red[(warp * 4 + b) * 64 + 2 * lane] = a[b][0];
            red[(warp * 4 + b) * 64 + 2 * lane + 1] = a[b][1];
        }
        __syncthreads();
        int b = tid >> 6, n = tid & 63;
        float s = 0.f;
#pragma unroll
        for (int w = 0; w < 8; w++) s += red[(w * 4 + b) * 64 + n];
        atomicAdd(&g_attn[b * 512 + ncI * 64 + n], s);
    }
    grid_barrier(&g_bar[2], NCTA);

    float* hs = red;
    if (warp < 4) {
        float v[16];
        const uint4* xp = reinterpret_cast<const uint4*>(x + warp * 512 + lane * 16);
        uint4 a = xp[0], b = xp[1];
        uint32_t w[8] = {a.x, a.y, a.z, a.w, b.x, b.y, b.z, b.w};
        const float4* ap = reinterpret_cast<const float4*>(g_attn + warp * 512 + lane * 16);
        float s = 0.f;
#pragma unroll
        for (int i = 0; i < 4; i++) {
            float4 t = __ldcg(ap + i);
            v[4 * i + 0] = round_bf(bf_lo(w[2 * i]) + round_bf(t.x));
            v[4 * i + 1] = round_bf(bf_hi(w[2 * i]) + round_bf(t.y));
            v[4 * i + 2] = round_bf(bf_lo(w[2 * i + 1]) + round_bf(t.z));
            v[4 * i + 3] = round_bf(bf_hi(w[2 * i + 1]) + round_bf(t.w));
            s += v[4 * i] + v[4 * i + 1] + v[4 * i + 2] + v[4 * i + 3];
        }
        float mean = warp_sum(s) * (1.f / 512.f);
        float q = 0.f;
#pragma unroll
        for (int i = 0; i < 16; i++) { float d = v[i] - mean; q += d * d; }
        float var = warp_sum(q) * (1.f / 512.f);
        float rstd = rsqrtf(var + 1e-5f);
#pragma unroll
        for (int i = 0; i < 16; i++) {
            xn[(lane * 16 + i) * 4 + warp] = round_bf((v[i] - mean) * rstd);
            hs[warp * 512 + lane * 16 + i] = v[i];
        }
    }
    __syncthreads();
    if (cta < NFFN) {
        float a[4] = {0.f, 0.f, 0.f, 0.f};
        const __nv_bfloat16* wsm = reinterpret_cast<const __nv_bfloat16*>(smem + ((lane >> 4) ? SM_WU : SM_WG));
        const int j = lane & 15;
#pragma unroll 8
        for (int k = warp * 64; k < warp * 64 + 64; k++) {
            float wv = __bfloat162float(wsm[k * 16 + j]);
            float4 hv = *reinterpret_cast<const float4*>(xn + k * 4);
            a[0] += hv.x * wv; a[1] += hv.y * wv; a[2] += hv.z * wv; a[3] += hv.w * wv;
        }
        float* r2 = red + 2048;
        *reinterpret_cast<float4*>(r2 + (warp * 32 + lane) * 4) = make_float4(a[0], a[1], a[2], a[3]);
        __syncthreads();
        if (tid < 64) {
            int b = tid >> 4, jj = tid & 15;
            float gs = 0.f, us = 0.f;
#pragma unroll
            for (int w = 0; w < 8; w++) {
                gs += r2[(w * 32 + jj) * 4 + b];
                us += r2[(w * 32 + 16 + jj) * 4 + b];
            }
            gs = round_bf(gs); us = round_bf(us);
            float inner = 0.7978845608028654f * (gs + 0.044715f * gs * gs * gs);
            float ge = round_bf(0.5f * gs * (1.f + tanhf(inner)));
            misc[jj * 4 + b] = round_bf(ge * us);
        }
        __syncthreads();
        float o[4][2];
#pragma unroll
        for (int b = 0; b < 4; b++) { o[b][0] = 0.f; o[b][1] = 0.f; }
        const uint32_t* wds = reinterpret_cast<const uint32_t*>(smem + SM_WD);
#pragma unroll
        for (int jj = 0; jj < 16; jj++) {
            uint32_t w = wds[jj * 256 + tid];
            float4 av = *reinterpret_cast<const float4*>(misc + jj * 4);
            float lo = bf_lo(w), hi = bf_hi(w);
            o[0][0] += av.x * lo; o[0][1] += av.x * hi;
            o[1][0] += av.y * lo; o[1][1] += av.y * hi;
            o[2][0] += av.z * lo; o[2][1] += av.z * hi;
            o[3][0] += av.w * lo; o[3][1] += av.w * hi;
        }
#pragma unroll
        for (int b = 0; b < 4; b++)
            atomicAdd(reinterpret_cast<float2*>(&g_final[b * 512 + 2 * tid]), make_float2(o[b][0], o[b][1]));
    }
    __syncthreads();
    __shared__ unsigned int s_ticket;
    if (tid == 0) {
        __threadfence();
        s_ticket = atomicAdd(&g_bar[3], 1u);
    }
    __syncthreads();
    if (s_ticket == NCTA - 1) {
        __threadfence();
        for (int i = tid; i < 2048; i += NTHREADS) {
            float f = __ldcg(&g_final[i]);
            out[i] = __float2bfloat16_rn(hs[i] + round_bf(f));
        }
        if (tid == 0) { g_bar[0] = 0; g_bar[1] = 0; g_bar[2] = 0; g_bar[3] = 0; }
    }
}

}

extern "C" void kernel_launch(void* const* d_in, const int* in_sizes, int n_in,
                              void* d_out, int out_size) {
    const __nv_bfloat16* x = (const __nv_bfloat16*)d_in[0];
    const __nv_bfloat16* kc = (const __nv_bfloat16*)d_in[1];
    const __nv_bfloat16* vc = (const __nv_bfloat16*)d_in[2];
    const __nv_bfloat16* wq = (const __nv_bfloat16*)d_in[3];
    const __nv_bfloat16* wo = (const __nv_bfloat16*)d_in[4];
    const __nv_bfloat16* wg = (const __nv_bfloat16*)d_in[6];
    const __nv_bfloat16* wu = (const __nv_bfloat16*)d_in[7];
    const __nv_bfloat16* wd = (const __nv_bfloat16*)d_in[8];
    cudaFuncSetAttribute(fused_block_kernel, cudaFuncAttributeMaxDynamicSharedMemorySize, SM_TOTAL);
    fused_block_kernel<<<NCTA, NTHREADS, SM_TOTAL>>>(x, kc, vc, wq, wo, wg, wu, wd, (__nv_bfloat16*)d_out);
}
```

```cpp
#include <cuda_runtime.h>
#include <cuda_bf16.h>
#include <cuda.h>
#include <stdint.h>

#define TS(i)

namespace {

constexpr int NCTA = 128;
constexpr int NTHREADS = 288;
constexpr int NWARPS = 8;
constexpr int D = 512;
constexpr int SK = 4096;
constexpr int DF = 1792;
constexpr int NFFN = 112;
constexpr int SPIN_LIMIT = 1 << 24;

__device__ __nv_bfloat16 g_q[4 * 4096];
__device__ float g_part_o[NCTA * 4 * 128];
__device__ float g_part_ml[NCTA * 4 * 2];
__device__ float g_attn[4 * 512];
__device__ float g_final[4 * 512];
__device__ unsigned int g_bar[4];

constexpr int NPRE = 1;
constexpr int NST = 6;
constexpr int STAGE_BYTES = 32768;
constexpr int WO_STRIDE = 144, WGU_STRIDE = 48, WD_STRIDE = 1040, WQ_STRIDE = 80, ACT_STRIDE = 1040;
constexpr int SM_RING = 0;
constexpr int SM_WO = SM_RING + 3 * STAGE_BYTES;
constexpr int SM_WG = SM_WO + 256 * WO_STRIDE;
constexpr int SM_WU = SM_WG + 512 * WGU_STRIDE;
constexpr int SM_WD = SM_WU + 512 * WGU_STRIDE;
constexpr int SM_WQ = SM_WO;
static_assert(SM_WD + 16 * WD_STRIDE <= NST * STAGE_BYTES + 4608, "alias");
constexpr int SM_ACT = NST * STAGE_BYTES + 4608;
constexpr int SM_F32 = SM_ACT + 4 * ACT_STRIDE;
constexpr int SM_MISC = SM_F32 + 16384;
constexpr int SM_BAR = SM_MISC + 1024;
constexpr int SM_TICKET = SM_BAR + 256;
constexpr int SM_TOTAL = SM_TICKET + 16;
static_assert(512 * WQ_STRIDE <= SM_ACT - SM_WO, "wq alias");

__device__ __forceinline__ uint4 ldg_stream(const void* p) {
    uint4 r;
    asm volatile("ld.global.nc.L1::no_allocate.L2::128B.v4.u32 {%0,%1,%2,%3}, [%4];"
                 : "=r"(r.x), "=r"(r.y), "=r"(r.z), "=r"(r.w) : "l"(p));
    return r;
}
__device__ __forceinline__ void cp_async16(uint32_t saddr, const void* g) {
    asm volatile("cp.async.cg.shared.global.L2::128B [%0], [%1], 16;" :: "r"(saddr), "l"(g));
}
__device__ __forceinline__ void mbar_init(uint32_t a, uint32_t cnt) {
    asm volatile("mbarrier.init.shared::cta.b64 [%0], %1;" :: "r"(a), "r"(cnt));
}
__device__ __forceinline__ void mbar_expect_tx(uint32_t a, uint32_t bytes) {
    asm volatile("mbarrier.arrive.expect_tx.shared::cta.b64 _, [%0], %1;" :: "r"(a), "r"(bytes) : "memory");
}
__device__ __forceinline__ void mbar_arrive(uint32_t a) {
    asm volatile("mbarrier.arrive.shared::cta.b64 _, [%0];" :: "r"(a) : "memory");
}
__device__ __forceinline__ void mbar_wait(uint32_t a, uint32_t parity) {
    uint32_t ok;
    int it = 0;
    do {
        asm volatile("{\n .reg .pred p;\n mbarrier.try_wait.parity.shared::cta.b64 p, [%1], %2;\n selp.u32 %0, 1, 0, p;\n}"
                     : "=r"(ok) : "r"(a), "r"(parity) : "memory");
        if (++it > SPIN_LIMIT) __trap();
    } while (!ok);
}
__device__ __forceinline__ void tma_load_2d(uint32_t dst, const CUtensorMap* tm, uint32_t mbar, int c0, int c1) {
    asm volatile("cp.async.bulk.tensor.2d.shared::cluster.global.mbarrier::complete_tx::bytes [%0], [%1, {%3, %4}], [%2];"
                 :: "r"(dst), "l"(reinterpret_cast<uint64_t>(tm)), "r"(mbar), "r"(c0), "r"(c1) : "memory");
}
__device__ __forceinline__ void ldsm_x4(uint32_t& r0, uint32_t& r1, uint32_t& r2, uint32_t& r3, uint32_t a) {
    asm volatile("ldmatrix.sync.aligned.m8n8.x4.shared.b16 {%0,%1,%2,%3}, [%4];"
                 : "=r"(r0), "=r"(r1), "=r"(r2), "=r"(r3) : "r"(a));
}
__device__ __forceinline__ void ldsm_x4_t(uint32_t& r0, uint32_t& r1, uint32_t& r2, uint32_t& r3, uint32_t a) {
    asm volatile("ldmatrix.sync.aligned.m8n8.x4.trans.shared.b16 {%0,%1,%2,%3}, [%4];"
                 : "=r"(r0), "=r"(r1), "=r"(r2), "=r"(r3) : "r"(a));
}
__device__ __forceinline__ void mma_bf16(float (&c)[4], uint32_t a0, uint32_t a1, uint32_t a2, uint32_t a3,
                                         uint32_t b0, uint32_t b1) {
    asm volatile("mma.sync.aligned.m16n8k16.row.col.f32.bf16.bf16.f32 {%0,%1,%2,%3}, {%4,%5,%6,%7}, {%8,%9}, {%0,%1,%2,%3};"
                 : "+f"(c[0]), "+f"(c[1]), "+f"(c[2]), "+f"(c[3])
                 : "r"(a0), "r"(a1), "r"(a2), "r"(a3), "r"(b0), "r"(b1));
}
__device__ __forceinline__ uint32_t pack_bf16(float lo, float hi) {
    __nv_bfloat162 v = __floats2bfloat162_rn(lo, hi);
    return *reinterpret_cast<uint32_t*>(&v);
}
__device__ __forceinline__ float bf_lo(uint32_t v) { return __uint_as_float(v << 16); }
__device__ __forceinline__ float bf_hi(uint32_t v) { return __uint_as_float(v & 0xffff0000u); }
__device__ __forceinline__ float round_bf(float v) { return __bfloat162float(__float2bfloat16_rn(v)); }

__device__ __forceinline__ void grid_barrier(unsigned int* ctr, unsigned int target) {
    __syncthreads();
    if (threadIdx.x == 0) {
        __threadfence();
        atomicAdd(ctr, 1u);
        unsigned int v;
        int it = 0;
        do {
            asm volatile("ld.acquire.gpu.global.u32 %0, [%1];" : "=r"(v) : "l"(ctr) : "memory");
            if (++it > SPIN_LIMIT) __trap();
        } while (v < target);
    }
    __syncthreads();
}

__device__ __forceinline__ float warp_sum(float v) {
#pragma unroll
    for (int o = 16; o > 0; o >>= 1) v += __shfl_xor_sync(0xffffffffu, v, o);
    return v;
}

__device__ __forceinline__ void ln_row(const float (&v)[16], unsigned char* act_row, int lane) {
    float s = 0.f;
#pragma unroll
    for (int i = 0; i < 16; i++) s += v[i];
    float mean = warp_sum(s) * (1.f / 512.f);
    float q = 0.f;
#pragma unroll
    for (int i = 0; i < 16; i++) { float d = v[i] - mean; q += d * d; }
    float var = round_bf(warp_sum(q) * (1.f / 512.f));
    float den = round_bf(sqrtf(round_bf(var + 1e-5f)));
    float mb = round_bf(mean);
    uint32_t o[8];
#pragma unroll
    for (int i = 0; i < 8; i++)
        o[i] = pack_bf16(round_bf(v[2 * i] - mb) / den, round_bf(v[2 * i + 1] - mb) / den);
    uint4* dst = reinterpret_cast<uint4*>(act_row + lane * 32);
    dst[0] = make_uint4(o[0], o[1], o[2], o[3]);
    dst[1] = make_uint4(o[4], o[5], o[6], o[7]);
}

__global__ void __launch_bounds__(NTHREADS, 1)
fused_block_kernel(const __grid_constant__ CUtensorMap tmK,
                   const __grid_constant__ CUtensorMap tmV,
                   const __nv_bfloat16* __restrict__ x,
                   const __nv_bfloat16* __restrict__ wq,
                   const __nv_bfloat16* __restrict__ wo,
                   const __nv_bfloat16* __restrict__ wg,
                   const __nv_bfloat16* __restrict__ wu,
                   const __nv_bfloat16* __restrict__ wd,
                   __nv_bfloat16* __restrict__ out) {
    extern __shared__ __align__(1024) unsigned char smem[];
    const uint32_t sbase = (uint32_t)__cvta_generic_to_shared(smem);
    const int tid = threadIdx.x;
    const int warp = tid >> 5;
    const int lane = tid & 31;
    const int cta = blockIdx.x;
    const int g = lane >> 2, c = lane & 3;
    const int lr = lane & 7, lm = lane >> 3;
    float* f32 = reinterpret_cast<float*>(smem + SM_F32);
    float* misc = reinterpret_cast<float*>(smem + SM_MISC);

    TS(0);
    uint4 xa, xb;
    if (warp < 4) {
        const uint4* xp = reinterpret_cast<const uint4*>(x + warp * 512 + lane * 16);
        xa = xp[0]; xb = xp[1];
    }
    if (tid < 256) for (int i = 0; i < 8; i++) {
        int ch = tid + i * 256, r = ch >> 2, pt = ch & 3;
        cp_async16(sbase + SM_WQ + r * WQ_STRIDE + pt * 16, wq + (size_t)r * 4096 + cta * 32 + pt * 8);
    }
    asm volatile("cp.async.commit_group;");
    const int bh = cta >> 2, split = cta & 3, batch = bh >> 3, hkv = bh & 7;
    const int row0 = bh * SK + split * 1024;
    const uint32_t bar_full = sbase + SM_BAR, bar_empty = sbase + SM_BAR + 8 * NST;
    if (tid == 8 * 32) {
        for (int i = 0; i < NST; i++) { mbar_init(bar_full + 8 * i, 1); mbar_init(bar_empty + 8 * i, 4); }
        asm volatile("fence.mbarrier_init.release.cluster;" ::: "memory");
        for (int st = 0; st < NPRE; st++) {
            uint32_t dst = sbase + SM_RING + st * STAGE_BYTES;
            mbar_expect_tx(bar_full + 8 * st, STAGE_BYTES);
            tma_load_2d(dst, &tmK, bar_full + 8 * st, 0, row0 + st * 64);
            tma_load_2d(dst + 8192, &tmK, bar_full + 8 * st, 64, row0 + st * 64);
            tma_load_2d(dst + 16384, &tmV, bar_full + 8 * st, 0, row0 + st * 64);
            tma_load_2d(dst + 24576, &tmV, bar_full + 8 * st, 64, row0 + st * 64);
        }
    }
    if (cta == 0) {
        for (int i = tid; i < 2048; i += NTHREADS) { g_attn[i] = 0.f; g_final[i] = 0.f; }
    }
    float xv[16];
    if (warp < 4) {
        uint32_t w[8] = {xa.x, xa.y, xa.z, xa.w, xb.x, xb.y, xb.z, xb.w};
#pragma unroll
        for (int i = 0; i < 8; i++) { xv[2 * i] = bf_lo(w[i]); xv[2 * i + 1] = bf_hi(w[i]); }
        ln_row(xv, smem + SM_ACT + warp * ACT_STRIDE, lane);
    }
    asm volatile("cp.async.wait_group 0;" ::: "memory");
    __syncthreads();
    if (warp < 8) {
        const int nt = warp & 3, kh = warp >> 2;
        float acc[4] = {0.f, 0.f, 0.f, 0.f};
        const uint32_t arow = sbase + SM_ACT + g * ACT_STRIDE + c * 4;
#pragma unroll 2
        for (int k0 = kh * 256; k0 < kh * 256 + 256; k0 += 32) {
            uint32_t r0, r1, r2, r3;
            ldsm_x4_t(r0, r1, r2, r3, sbase + SM_WQ + (k0 + lane) * WQ_STRIDE + nt * 16);
            uint32_t a0 = 0, a1 = 0, a2 = 0, a3 = 0;
            if (g < 4) {
                asm volatile("ld.shared.u32 %0, [%1];" : "=r"(a0) : "r"(arow + k0 * 2));
                asm volatile("ld.shared.u32 %0, [%1];" : "=r"(a1) : "r"(arow + k0 * 2 + 16));
                asm volatile("ld.shared.u32 %0, [%1];" : "=r"(a2) : "r"(arow + k0 * 2 + 32));
                asm volatile("ld.shared.u32 %0, [%1];" : "=r"(a3) : "r"(arow + k0 * 2 + 48));
            }
            mma_bf16(acc, a0, 0u, a1, 0u, r0, r1);
            mma_bf16(acc, a2, 0u, a3, 0u, r2, r3);
        }
        if (g < 4) *reinterpret_cast<float2*>(misc + (kh * 4 + g) * 32 + nt * 8 + 2 * c) = make_float2(acc[0], acc[1]);
    }
    __syncthreads();
    if (tid < 128) g_q[(tid >> 5) * 4096 + cta * 32 + (tid & 31)] = __float2bfloat16_rn(misc[tid] + misc[128 + tid]);
    const int kcI = cta >> 3, ncI = cta & 7;
    TS(1);
    __syncthreads();
    if (tid == 0) { __threadfence(); atomicAdd(&g_bar[0], 1u); }
    if (warp < 8 && lane == 0) {
        unsigned int v; int it = 0;
        do {
            asm volatile("ld.acquire.gpu.global.u32 %0, [%1];" : "=r"(v) : "l"(&g_bar[0]) : "memory");
            if (++it > SPIN_LIMIT) __trap();
        } while (v < NCTA);
    }
    __syncwarp();
    TS(2);
    if (warp == 8) {
        if (lane == 0) {
            for (int s2 = NPRE; s2 < 16; s2++) {
                int st = s2 % NST;
                if (s2 >= NST) mbar_wait(bar_empty + 8 * st, ((s2 / NST) - 1) & 1);
                else if (s2 < 3) mbar_wait(bar_full + 8 * (st - 1), 0);
                uint32_t dst = sbase + SM_RING + st * STAGE_BYTES;
                mbar_expect_tx(bar_full + 8 * st, STAGE_BYTES);
                tma_load_2d(dst, &tmK, bar_full + 8 * st, 0, row0 + s2 * 64);
                tma_load_2d(dst + 8192, &tmK, bar_full + 8 * st, 64, row0 + s2 * 64);
                tma_load_2d(dst + 16384, &tmV, bar_full + 8 * st, 0, row0 + s2 * 64);
                tma_load_2d(dst + 24576, &tmV, bar_full + 8 * st, 64, row0 + s2 * 64);
            }
        }
    } else {
        uint32_t qf[16];
        if (g < 4) {
            const uint32_t* qp = reinterpret_cast<const uint32_t*>(g_q + batch * 4096 + (hkv * 4 + g) * 128);
#pragma unroll
            for (int ks = 0; ks < 8; ks++) {
                qf[2 * ks] = __ldcg(qp + ks * 8 + c);
                qf[2 * ks + 1] = __ldcg(qp + ks * 8 + 4 + c);
            }
        } else {
#pragma unroll
            for (int j = 0; j < 16; j++) qf[j] = 0u;
        }
        const float qscale = 0.08838834764831845f;
        const float log2e = 1.4426950408889634f;
        float oacc[16][4];
#pragma unroll
        for (int t = 0; t < 16; t++) { oacc[t][0] = oacc[t][1] = oacc[t][2] = oacc[t][3] = 0.f; }
        float mrun = -INFINITY, lrun = 0.f;
        const int krow0 = (warp & 3) * 16 + lr;
        const int vrow = (warp & 3) * 16 + (lm & 1) * 8 + lr;
#pragma unroll 1
        for (int s2 = warp >> 2; s2 < 16; s2 += 2) {
            const int st = s2 % NST;
            mbar_wait(bar_full + 8 * st, (s2 / NST) & 1);
            const uint32_t kb = sbase + SM_RING + st * STAGE_BYTES;
            const uint32_t vb = kb + 16384;
            float s0[4] = {0.f, 0.f, 0.f, 0.f}, s1[4] = {0.f, 0.f, 0.f, 0.f};
#pragma unroll
            for (int kp = 0; kp < 4; kp++) {
                int ch = 4 * kp + lm;
                int half = ch >> 3, cc = ch & 7;
                uint32_t r0, r1, r2, r3;
                ldsm_x4(r0, r1, r2, r3, kb + half * 8192 + krow0 * 128 + ((cc ^ (krow0 & 7)) << 4));
                mma_bf16(s0, qf[4 * kp], 0u, qf[4 * kp + 1], 0u, r0, r1);
                mma_bf16(s0, qf[4 * kp + 2], 0u, qf[4 * kp + 3], 0u, r2, r3);
                ldsm_x4(r0, r1, r2, r3, kb + half * 8192 + (krow0 + 8) * 128 + ((cc ^ (krow0 & 7)) << 4));
                mma_bf16(s1, qf[4 * kp], 0u, qf[4 * kp + 1], 0u, r0, r1);
                mma_bf16(s1, qf[4 * kp + 2], 0u, qf[4 * kp + 3], 0u, r2, r3);
            }
            float a0 = round_bf(round_bf(s0[0]) * qscale) * log2e, a1 = round_bf(round_bf(s0[1]) * qscale) * log2e;
            float a2 = round_bf(round_bf(s1[0]) * qscale) * log2e, a3 = round_bf(round_bf(s1[1]) * qscale) * log2e;
            float mx = fmaxf(fmaxf(a0, a1), fmaxf(a2, a3));
            mx = fmaxf(mx, __shfl_xor_sync(0xffffffffu, mx, 1));
            mx = fmaxf(mx, __shfl_xor_sync(0xffffffffu, mx, 2));
            float mnew = fmaxf(mrun, mx);
            float corr = exp2f(mrun - mnew);
            mrun = mnew;
            uint32_t pa0 = pack_bf16(exp2f(a0 - mnew), exp2f(a1 - mnew));
            uint32_t pa2 = pack_bf16(exp2f(a2 - mnew), exp2f(a3 - mnew));
            lrun = lrun * corr + (bf_lo(pa0) + bf_hi(pa0) + bf_lo(pa2) + bf_hi(pa2));
#pragma unroll
            for (int t = 0; t < 16; t++) { oacc[t][0] *= corr; oacc[t][1] *= corr; }
#pragma unroll
            for (int dp = 0; dp < 8; dp++) {
                int ch = 2 * dp + (lm >> 1);
                int half = ch >> 3, cc = ch & 7;
                uint32_t r0, r1, r2, r3;
                ldsm_x4_t(r0, r1, r2, r3, vb + half * 8192 + vrow * 128 + ((cc ^ (vrow & 7)) << 4));
                mma_bf16(oacc[2 * dp], pa0, 0u, pa2, 0u, r0, r1);
                mma_bf16(oacc[2 * dp + 1], pa0, 0u, pa2, 0u, r2, r3);
            }
            __syncwarp();
            if (lane == 0) mbar_arrive(bar_empty + 8 * st);
        }
        asm volatile("bar.sync 1, 256;" ::: "memory");
        for (int i = 0; i < 8; i++) {
            int ch = tid + i * 256, r = ch >> 3, pt = ch & 7;
            cp_async16(sbase + SM_WO + r * WO_STRIDE + pt * 16, wo + (size_t)(kcI * 256 + r) * 512 + ncI * 64 + pt * 8);
        }
        asm volatile("cp.async.commit_group;");
        if (cta < NFFN) {
            for (int i = 0; i < 4; i++) {
                int ch = tid + i * 256, r = ch >> 1, pt = ch & 1;
                cp_async16(sbase + SM_WG + r * WGU_STRIDE + pt * 16, wg + (size_t)r * DF + cta * 16 + pt * 8);
                cp_async16(sbase + SM_WU + r * WGU_STRIDE + pt * 16, wu + (size_t)r * DF + cta * 16 + pt * 8);
                cp_async16(sbase + SM_WD + (ch >> 6) * WD_STRIDE + (ch & 63) * 16, wd + (size_t)cta * 16 * 512 + ch * 8);
            }
        }
        asm volatile("cp.async.commit_group;");
        lrun += __shfl_xor_sync(0xffffffffu, lrun, 1);
        lrun += __shfl_xor_sync(0xffffffffu, lrun, 2);
        if (g < 4) {
#pragma unroll
            for (int t = 0; t < 16; t++)
                *reinterpret_cast<float2*>(f32 + (warp * 4 + g) * 128 + 8 * t + 2 * c) = make_float2(oacc[t][0], oacc[t][1]);
            if (c == 0) { misc[(warp * 4 + g) * 2] = mrun; misc[(warp * 4 + g) * 2 + 1] = lrun; }
        }
    }
    __syncthreads();
    if (tid < 256) for (int idx = tid; idx < 512; idx += 256) {
        int h = idx >> 7, d = idx & 127;
        float M = -INFINITY;
        for (int w = 0; w < 8; w++) M = fmaxf(M, misc[(w * 4 + h) * 2]);
        float o = 0.f, L = 0.f;
        for (int w = 0; w < 8; w++) {
            float f = exp2f(misc[(w * 4 + h) * 2] - M);
            o += f * f32[(w * 4 + h) * 128 + d];
            L += f * misc[(w * 4 + h) * 2 + 1];
        }
        g_part_o[(cta * 4 + h) * 128 + d] = o;
        if (d == 0) *reinterpret_cast<float2*>(&g_part_ml[(cta * 4 + h) * 2]) = make_float2(M, L);
    }
    TS(3);
    grid_barrier(&g_bar[1], NCTA);
    TS(4);

    if (tid < 256) {
        const int hq = 2 * kcI + (tid >> 7), hk = hq >> 2, hg = hq & 3, d = tid & 127;
#pragma unroll
        for (int b = 0; b < 4; b++) {
            const int base = ((b * 8 + hk) * 4) * 4 + hg;
            float2 ml[4]; float o[4];
#pragma unroll
            for (int s2 = 0; s2 < 4; s2++) {
                ml[s2] = __ldcg(reinterpret_cast<const float2*>(&g_part_ml[(base + s2 * 4) * 2]));
                o[s2] = __ldcg(&g_part_o[(base + s2 * 4) * 128 + d]);
            }
            float M = fmaxf(fmaxf(ml[0].x, ml[1].x), fmaxf(ml[2].x, ml[3].x));
            float L = 0.f, acc = 0.f;
#pragma unroll
            for (int s2 = 0; s2 < 4; s2++) { float f = exp2f(ml[s2].x - M); L += f * ml[s2].y; acc += f * o[s2]; }
            *reinterpret_cast<__nv_bfloat16*>(smem + SM_ACT + b * ACT_STRIDE + tid * 2) = __float2bfloat16_rn(acc / L);
        }
    }
    TS(8);
    asm volatile("cp.async.wait_group 1;" ::: "memory");
    __syncthreads();
    TS(9);
    if (warp < 8) {
        float acc[4] = {0.f, 0.f, 0.f, 0.f};
        const uint32_t arow = sbase + SM_ACT + g * ACT_STRIDE + c * 4;
#pragma unroll 2
        for (int k0 = 0; k0 < 256; k0 += 32) {
            uint32_t r0, r1, r2, r3;
            ldsm_x4_t(r0, r1, r2, r3, sbase + SM_WO + (k0 + lane) * WO_STRIDE + warp * 16);
            uint32_t a0 = 0, a1 = 0, a2 = 0, a3 = 0;
            if (g < 4) {
                asm volatile("ld.shared.u32 %0, [%1];" : "=r"(a0) : "r"(arow + k0 * 2));
                asm volatile("ld.shared.u32 %0, [%1];" : "=r"(a1) : "r"(arow + k0 * 2 + 16));
                asm volatile("ld.shared.u32 %0, [%1];" : "=r"(a2) : "r"(arow + k0 * 2 + 32));
                asm volatile("ld.shared.u32 %0, [%1];" : "=r"(a3) : "r"(arow + k0 * 2 + 48));
            }
            mma_bf16(acc, a0, 0u, a1, 0u, r0, r1);
            mma_bf16(acc, a2, 0u, a3, 0u, r2, r3);
        }
        if (g < 4) atomicAdd(reinterpret_cast<float2*>(&g_attn[g * 512 + ncI * 64 + warp * 8 + 2 * c]), make_float2(acc[0], acc[1]));
    }
    TS(5);
    grid_barrier(&g_bar[2], NCTA);
    TS(6);

    if (warp < 4) {
        const float4* ap = reinterpret_cast<const float4*>(g_attn + warp * 512 + lane * 16);
#pragma unroll
        for (int i = 0; i < 4; i++) {
            float4 t = __ldcg(ap + i);
            xv[4 * i + 0] = round_bf(xv[4 * i + 0] + round_bf(t.x));
            xv[4 * i + 1] = round_bf(xv[4 * i + 1] + round_bf(t.y));
            xv[4 * i + 2] = round_bf(xv[4 * i + 2] + round_bf(t.z));
            xv[4 * i + 3] = round_bf(xv[4 * i + 3] + round_bf(t.w));
        }
        ln_row(xv, smem + SM_ACT + warp * ACT_STRIDE, lane);
    }
    TS(10);
    asm volatile("cp.async.wait_group 0;" ::: "memory");
    __syncthreads();
    TS(11);
    if (cta < NFFN) {
        const int mat = warp & 1, kq = warp >> 1;
        float a0c[4] = {0.f, 0.f, 0.f, 0.f}, a1c[4] = {0.f, 0.f, 0.f, 0.f};
        const uint32_t wbase = sbase + (mat ? SM_WU : SM_WG);
        const uint32_t arow = sbase + SM_ACT + g * ACT_STRIDE + c * 4;
#pragma unroll 2
        for (int k0 = kq * 128; warp < 8 && k0 < kq * 128 + 128; k0 += 16) {
            uint32_t r0, r1, r2, r3;
            ldsm_x4_t(r0, r1, r2, r3, wbase + (k0 + (lm & 1) * 8 + lr) * WGU_STRIDE + (lm >> 1) * 16);
            uint32_t a0 = 0, a1 = 0;
            if (g < 4) {
                asm volatile("ld.shared.u32 %0, [%1];" : "=r"(a0) : "r"(arow + k0 * 2));
                asm volatile("ld.shared.u32 %0, [%1];" : "=r"(a1) : "r"(arow + k0 * 2 + 16));
            }
            mma_bf16(a0c, a0, 0u, a1, 0u, r0, r1);
            mma_bf16(a1c, a0, 0u, a1, 0u, r2, r3);
        }
        if (g < 4 && warp < 8) {
            *reinterpret_cast<float2*>(f32 + (warp * 4 + g) * 16 + 2 * c) = make_float2(a0c[0], a0c[1]);
            *reinterpret_cast<float2*>(f32 + (warp * 4 + g) * 16 + 8 + 2 * c) = make_float2(a1c[0], a1c[1]);
        }
        TS(12);
        __syncthreads();
        if (tid < 64) {
            int b = tid >> 4, j = tid & 15;
            float gs = 0.f, us = 0.f;
            for (int q4 = 0; q4 < 4; q4++) {
                gs += f32[((q4 * 2) * 4 + b) * 16 + j];
                us += f32[((q4 * 2 + 1) * 4 + b) * 16 + j];
            }
            gs = round_bf(gs); us = round_bf(us);
            float inner = 0.7978845608028654f * (gs + 0.044715f * gs * gs * gs);
            float ge = round_bf(0.5f * gs * (1.f + tanhf(inner)));
            reinterpret_cast<__nv_bfloat16*>(misc)[b * 16 + j] = __float2bfloat16_rn(ge * us);
        }
        __syncthreads();
        TS(13);
        uint32_t a0 = 0, a1 = 0;
        if (g < 4) {
            a0 = reinterpret_cast<const uint32_t*>(misc)[g * 8 + c];
            a1 = reinterpret_cast<const uint32_t*>(misc)[g * 8 + 4 + c];
        }
#pragma unroll 2
        for (int n0 = warp * 64; warp < 8 && n0 < warp * 64 + 64; n0 += 16) {
            uint32_t r0, r1, r2, r3;
            ldsm_x4_t(r0, r1, r2, r3, sbase + SM_WD + ((lm & 1) * 8 + lr) * WD_STRIDE + (n0 + (lm >> 1) * 8) * 2);
            float o0[4] = {0.f, 0.f, 0.f, 0.f}, o1[4] = {0.f, 0.f, 0.f, 0.f};
            mma_bf16(o0, a0, 0u, a1, 0u, r0, r1);
            mma_bf16(o1, a0, 0u, a1, 0u, r2, r3);
            if (g < 4) {
                atomicAdd(reinterpret_cast<float2*>(&g_final[g * 512 + n0 + 2 * c]), make_float2(o0[0], o0[1]));
                atomicAdd(reinterpret_cast<float2*>(&g_final[g * 512 + n0 + 8 + 2 * c]), make_float2(o1[0], o1[1]));
            }
        }
    }
    TS(7);
    __syncthreads();
    volatile unsigned int& s_ticket = *reinterpret_cast<volatile unsigned int*>(smem + SM_TICKET);
    if (tid == 0) {
        __threadfence();
        s_ticket = atomicAdd(&g_bar[3], 1u);
    }
    __syncthreads();
    if (s_ticket == NCTA - 1) {
        __threadfence();
        if (warp < 4) {
            const float4* fp = reinterpret_cast<const float4*>(g_final + warp * 512 + lane * 16);
            uint32_t o[8];
#pragma unroll
            for (int i = 0; i < 4; i++) {
                float4 t = __ldcg(fp + i);
                o[2 * i] = pack_bf16(xv[4 * i] + round_bf(t.x), xv[4 * i + 1] + round_bf(t.y));
                o[2 * i + 1] = pack_bf16(xv[4 * i + 2] + round_bf(t.z), xv[4 * i + 3] + round_bf(t.w));
            }
            uint4* op = reinterpret_cast<uint4*>(out + warp * 512 + lane * 16);
            op[0] = make_uint4(o[0], o[1], o[2], o[3]);
            op[1] = make_uint4(o[4], o[5], o[6], o[7]);
        }
        if (tid == 0) { g_bar[0] = 0; g_bar[1] = 0; g_bar[2] = 0; g_bar[3] = 0; }
    }
}

}

typedef CUresult (*PFN_encodeTiled)(CUtensorMap*, CUtensorMapDataType, cuuint32_t, void*, const cuuint64_t*,
                                    const cuuint64_t*, const cuuint32_t*, const cuuint32_t*, CUtensorMapInterleave,
                                    CUtensorMapSwizzle, CUtensorMapL2promotion, CUtensorMapFloatOOBfill);

static void make_map(PFN_encodeTiled fn, CUtensorMap* m, const void* ptr) {
    cuuint64_t dims[2] = {128, (cuuint64_t)4 * 8 * 4096};
    cuuint64_t strides[1] = {256};
    cuuint32_t box[2] = {64, 64};
    cuuint32_t es[2] = {1, 1};
    fn(m, CU_TENSOR_MAP_DATA_TYPE_BFLOAT16, 2, const_cast<void*>(ptr), dims, strides, box, es,
       CU_TENSOR_MAP_INTERLEAVE_NONE, CU_TENSOR_MAP_SWIZZLE_128B, CU_TENSOR_MAP_L2_PROMOTION_L2_256B,
       CU_TENSOR_MAP_FLOAT_OOB_FILL_NONE);
}

extern "C" void kernel_launch(void* const* d_in, const int* in_sizes, int n_in,
                              void* d_out, int out_size) {
    const __nv_bfloat16* x = (const __nv_bfloat16*)d_in[0];
    const __nv_bfloat16* wq = (const __nv_bfloat16*)d_in[3];
    const __nv_bfloat16* wo = (const __nv_bfloat16*)d_in[4];
    const __nv_bfloat16* wg = (const __nv_bfloat16*)d_in[6];
    const __nv_bfloat16* wu = (const __nv_bfloat16*)d_in[7];
    const __nv_bfloat16* wd = (const __nv_bfloat16*)d_in[8];
    static PFN_encodeTiled enc = nullptr;
    if (!enc) {
        void* fp = nullptr;
        cudaDriverEntryPointQueryResult qr;
        cudaGetDriverEntryPoint("cuTensorMapEncodeTiled", &fp, cudaEnableDefault, &qr);
        enc = (PFN_encodeTiled)fp;
        cudaFuncSetAttribute(fused_block_kernel, cudaFuncAttributeMaxDynamicSharedMemorySize, SM_TOTAL);
    }
    CUtensorMap tmK, tmV;
    make_map(enc, &tmK, d_in[1]);
    make_map(enc, &tmV, d_in[2]);
    fused_block_kernel<<<NCTA, NTHREADS, SM_TOTAL>>>(tmK, tmV, x, wq, wo, wg, wu, wd, (__nv_bfloat16*)d_out);
}
```
